```python
import torch

def _softmax(x, axis=-1):
    return torch.softmax(x, dim=axis)
def _gelu(x):
    return torch.nn.functional.gelu(x, approximate="tanh")
def _silu(x):
    return torch.nn.functional.silu(x)
def _sigmoid(x):
    return torch.sigmoid(x)
def _layernorm(x, axis=-1, eps=1e-5):
    m = x.mean(dim=axis, keepdim=True)
    v = x.var(dim=axis, keepdim=True, unbiased=False)
    return (x - m) / torch.sqrt(v + eps)
def _scatter_add(tgt, idx, src, axis=0):
    return tgt.clone().index_add_(axis, idx, src)
def _segment_sum(src, seg, n):
    out = torch.zeros((n,) + src.shape[1:], dtype=src.dtype)
    return out.index_add_(0, seg, src)
def _pad(x, pw):
    flat = tuple(v for pair in reversed(pw) for v in pair)
    return torch.nn.functional.pad(x, flat)

kernel_name = 'recurrent_scan__ssm_conv_s5__glu_gated_reglu__prompt'

def setup_inputs():

    _w = (lambda a: (lambda t: t.to(torch.bfloat16) if t.is_floating_point() else t)(torch.as_tensor(a)))
    def _A_setup():
        B, S, D = 1, 2048, 512
        P = D
        Lambda_re = -0.5 * (lambda _x: torch.exp(torch.as_tensor(_x)))((lambda *s: torch.randn(*s, dtype=torch.bfloat16) * 0.8)(P))
        Lambda_im = (lambda *s: torch.randn(*s, dtype=torch.bfloat16) * 0.8)(P) * 1.0
        B_re = (lambda *s: torch.randn(*s, dtype=torch.bfloat16) * 0.8)(P, D) * (D ** -0.5)
        B_im = (lambda *s: torch.randn(*s, dtype=torch.bfloat16) * 0.8)(P, D) * (D ** -0.5)
        C_re = (lambda *s: torch.randn(*s, dtype=torch.bfloat16) * 0.8)(D, P) * (P ** -0.5)
        C_im = (lambda *s: torch.randn(*s, dtype=torch.bfloat16) * 0.8)(D, P) * (P ** -0.5)
        log_dt = (lambda *s: torch.randn(*s, dtype=torch.bfloat16) * 0.8)(P) * 0.3 - 2.0
        Dskip = (lambda *s: torch.randn(*s, dtype=torch.bfloat16) * 0.8)(D)
        return {
            "x": _w((lambda *s: torch.randn(*s, dtype=torch.bfloat16) * 0.05)(B, S, D)),
            "Lambda_re": _w(Lambda_re),
            "Lambda_im": _w(Lambda_im),
            "B_re": _w(B_re),
            "B_im": _w(B_im),
            "C_re": _w(C_re),
            "C_im": _w(C_im),
            "log_dt": _w(log_dt),
            "Dskip": _w(Dskip),
        }
    _A_in = _A_setup()

    def _B_setup():
        B, S, D, F = 1, 2048, 512, 1376
        return {
            "x": _w((lambda *s: torch.randn(*s, dtype=torch.bfloat16) * 0.05)(B, S, D)),
            "W_gate": _w((lambda *s: torch.randn(*s, dtype=torch.bfloat16) * 0.2)(D, F) * (2.0 / D) ** 0.5),
            "W_up": _w((lambda *s: torch.randn(*s, dtype=torch.bfloat16) * 0.2)(D, F) * (2.0 / D) ** 0.5),
            "W_down": _w((lambda *s: torch.randn(*s, dtype=torch.bfloat16) * 0.2)(F, D) * (1.0 / F) ** 0.5),
        }
    _B_in = _B_setup()

    return {
        "A_x": _A_in["x"],
        "A_Lambda_re": _A_in["Lambda_re"],
        "A_Lambda_im": _A_in["Lambda_im"],
        "A_B_re": _A_in["B_re"],
        "A_B_im": _A_in["B_im"],
        "A_C_re": _A_in["C_re"],
        "A_C_im": _A_in["C_im"],
        "A_log_dt": _A_in["log_dt"],
        "A_Dskip": _A_in["Dskip"],
        "B_x": _B_in["x"],
        "B_W_gate": _B_in["W_gate"],
        "B_W_up": _B_in["W_up"],
        "B_W_down": _B_in["W_down"],
    }

def reference(A_x, A_Lambda_re, A_Lambda_im, A_B_re, A_B_im, A_C_re, A_C_im, A_log_dt, A_Dskip, B_x, B_W_gate, B_W_up, B_W_down):
    def _A_ref(x, Lambda_re, Lambda_im, B_re, B_im, C_re, C_im, log_dt, Dskip):
        Bsz, L, H = x.shape
        Lam = Lambda_re + 1j * Lambda_im
        Bmat = B_re + 1j * B_im
        Cmat = C_re + 1j * C_im
        dt = torch.exp(log_dt)
        Lam_bar = torch.exp(dt * Lam)
        B_bar = ((Lam_bar - 1.0) / Lam)[:, None] * Bmat
        Bu = torch.einsum("bld,pd->blp", x + 0j, B_bar)
        h = torch.zeros_like(Bu[:, 0, :])
        hs = []
        for t in range(L):
            h = Lam_bar[None, :] * h + Bu[:, t, :]
            hs.append(h)
        hseq = torch.stack(hs, 1)
        y = 2.0 * torch.einsum("blp,dp->bld", hseq, Cmat).real + x * Dskip[None, None, :]
        return y

    def _B_ref(x, W_gate, W_up, W_down):
        gate = torch.einsum("bsd,df->bsf", x, W_gate)
        up = torch.einsum("bsd,df->bsf", x, W_up)
        gate = gate * (lambda x, dt: x.to(dt))(gate > 0, gate.dtype)
        h = gate * up
        return torch.einsum("bsf,fd->bsd", h, W_down)

    x = A_x
    xn = _layernorm(x, axis=-1)
    s = _A_ref(xn, A_Lambda_re, A_Lambda_im, A_B_re, A_B_im, A_C_re, A_C_im, A_log_dt, A_Dskip)
    g = _silu(_B_ref(xn, B_W_gate, B_W_up, B_W_down))
    return x + s * g
```

```cpp
#include <cuda_runtime.h>
#include <cuda_bf16.h>
#include <cuda.h>
#include <stdint.h>

namespace {

typedef __nv_bfloat16 bf16;
typedef unsigned long long u64;

constexpr int FF = 1376;
constexpr int NSLOT = 14;
constexpr uint32_t SLOT = 16384;
constexpr int KG_TOT = 300;
constexpr uint32_t OFF_STATS = NSLOT * SLOT;
constexpr uint32_t OFF_CS = OFF_STATS + 1088;
constexpr uint32_t OFF_BAR = OFF_CS + 1408;
constexpr uint32_t B_FULL = OFF_BAR, B_EMPTY = OFF_BAR + 8 * NSLOT, B_ORD = OFF_BAR + 16 * NSLOT;
constexpr uint32_t B_PUB = B_ORD + 32, B_XDONE = B_PUB + 32, B_CS = B_XDONE + 8, B_STATS = B_CS + 8, B_G = B_STATS + 8;
constexpr int NBAR = 2 * NSLOT + 12;
constexpr uint32_t SMEM_BYTES = OFF_BAR + 8 * NBAR;
constexpr uint32_t OFF_G = 5 * SLOT;
#define GOD 2100
constexpr uint32_t GO_DELAY_NS = GOD;
constexpr uint32_t SPIN_LIMIT = 1u << 17;

struct Params {
    CUtensorMap tmX, tmB, tmWg, tmWu, tmC1, tmC2, tmWd, tmXh;
    const bf16 *x, *lam_re, *lam_im, *log_dt, *dskip, *B1, *B2, *Wg, *Wu, *C1, *C2, *Wd;
    float* out;
    unsigned char* h;
    uint32_t *stats, *bsum, *csum, *E;
    unsigned *flag, *sync;
    uint32_t zero;
    float sw;
};

__device__ __align__(1024) unsigned char g_h[32 * KG_TOT * 1024];
__device__ __align__(128) uint32_t g_stats[2048 * 2];
__device__ __align__(128) uint32_t g_bsum[2048];
__device__ __align__(128) uint32_t g_csum[8 * 2 * 1408];
__device__ __align__(128) uint32_t g_E[16 * 512 * 2];
__device__ __align__(128) unsigned g_flag[128 * 8];
__device__ __align__(128) unsigned g_sync[64] = {1u};
#define PROF_ONE(i)
#define PROF(i)
#define PROFW(i)

__device__ __forceinline__ void mbar_init(uint32_t bar, uint32_t cnt) {
    asm volatile("mbarrier.init.shared::cta.b64 [%0], %1;" ::"r"(bar), "r"(cnt) : "memory");
}
__device__ __forceinline__ void mbar_expect_tx(uint32_t bar, uint32_t bytes) {
    asm volatile("mbarrier.arrive.expect_tx.shared::cta.b64 _, [%0], %1;" ::"r"(bar), "r"(bytes) : "memory");
}
__device__ __forceinline__ void mbar_arrive(uint32_t bar) {
    asm volatile("mbarrier.arrive.shared::cta.b64 _, [%0];" ::"r"(bar) : "memory");
}
__device__ __forceinline__ void mbar_arrive2_if(bool c, uint32_t b0, uint32_t b1) {
    asm volatile("{\n.reg .pred p;\nsetp.ne.u32 p, %2, 0;\n@p mbarrier.arrive.shared::cta.b64 _, [%0];\n"
                 "@p mbarrier.arrive.shared::cta.b64 _, [%1];\n}" ::"r"(b0), "r"(b1), "r"((uint32_t)c) : "memory");
}
#define TRAP_S "trap;"
__device__ __forceinline__ void mbar_wait(uint32_t bar, uint32_t parity) {
    asm volatile(
        "{\n.reg .pred p;\n.reg .u32 c;\nmov.u32 c, 0;\n"
        "LW:\nmbarrier.try_wait.parity.shared::cta.b64 p, [%0], %1;\n@p bra LD;\n"
        "add.u32 c, c, 1;\nsetp.lt.u32 p, c, 0x20000;\n@p bra LW;\ntrap;\nLD:\n}" ::"r"(bar), "r"(parity)
        : "memory");
}
__device__ __forceinline__ uint32_t mbar_test(uint32_t bar, uint32_t parity) {
    uint32_t ok;
    asm volatile("{\n.reg .pred p;\nmbarrier.test_wait.parity.shared::cta.b64 p, [%1], %2;\nselp.u32 %0, 1, 0, p;\n}"
                 : "=r"(ok) : "r"(bar), "r"(parity) : "memory");
    return ok;
}
__device__ __forceinline__ void mbar_wait_if(uint32_t ok, uint32_t bar, uint32_t parity) {
    asm volatile(
        "{\n.reg .pred p;\n.reg .u32 c;\nsetp.ne.u32 p, %2, 0;\n@p bra LD;\nmov.u32 c, 0;\n"
        "LW:\nmbarrier.try_wait.parity.shared::cta.b64 p, [%0], %1;\n@p bra LD;\n"
        "add.u32 c, c, 1;\nsetp.lt.u32 p, c, 0x20000;\n@p bra LW;\ntrap;\nLD:\n}" ::"r"(bar), "r"(parity), "r"(ok)
        : "memory");
}
__device__ __forceinline__ uint32_t ld_epoch(const unsigned* p) {
    uint32_t v;
    asm volatile("ld.relaxed.gpu.global.u32 %0, [%1];" : "=r"(v) : "l"(p) : "memory");
    return v;
}
__device__ __forceinline__ void spin_check(uint32_t& spins) {
    if (++spins > SPIN_LIMIT) asm volatile("trap;");
}
__device__ __forceinline__ bool elect_one() {
    uint32_t p;
    asm volatile("{.reg .pred P; elect.sync _|P, 0xffffffff; selp.u32 %0, 1, 0, P;}" : "=r"(p));
    return p != 0;
}
__device__ __forceinline__ void tma2(uint32_t dst, const CUtensorMap* tm, uint32_t bar, int c0, int c1) {
    asm volatile("cp.async.bulk.tensor.2d.shared::cluster.global.mbarrier::complete_tx::bytes [%0], [%1, {%3,%4}], [%2];"
                 ::"r"(dst), "l"(tm), "r"(bar), "r"(c0), "r"(c1) : "memory");
}
__device__ __forceinline__ void tma3(uint32_t dst, const CUtensorMap* tm, uint32_t bar, int c0, int c1, int c2) {
    asm volatile("cp.async.bulk.tensor.3d.shared::cluster.global.mbarrier::complete_tx::bytes [%0], [%1, {%3,%4,%5}], [%2];"
                 ::"r"(dst), "l"(tm), "r"(bar), "r"(c0), "r"(c1), "r"(c2) : "memory");
}
__device__ __forceinline__ void tma4(uint32_t dst, const CUtensorMap* tm, uint32_t bar, int c0, int c3) {
    asm volatile("cp.async.bulk.tensor.4d.shared::cluster.global.mbarrier::complete_tx::bytes [%0], [%1, {%3,%4,%4,%5}], [%2];"
                 ::"r"(dst), "l"(tm), "r"(bar), "r"(c0), "r"(0), "r"(c3) : "memory");
}
__device__ __forceinline__ void tma5(uint32_t dst, const CUtensorMap* tm, uint32_t bar, int c0, int c4) {
    asm volatile("cp.async.bulk.tensor.5d.shared::cluster.global.mbarrier::complete_tx::bytes [%0], [%1, {%3,%4,%4,%4,%5}], [%2];"
                 ::"r"(dst), "l"(tm), "r"(bar), "r"(c0), "r"(0), "r"(c4) : "memory");
}
__device__ __forceinline__ void tma5h(uint32_t dst, const CUtensorMap* tm, uint32_t bar, int c0, int c3, int c4) {
    asm volatile("cp.async.bulk.tensor.5d.shared::cluster.global.mbarrier::complete_tx::bytes [%0], [%1, {%3,%4,%4,%5,%6}], [%2];"
                 ::"r"(dst), "l"(tm), "r"(bar), "r"(c0), "r"(0), "r"(c3), "r"(c4) : "memory");
}
__device__ __forceinline__ void bulk_g2s(uint32_t dst, const void* src, uint32_t bytes, uint32_t bar) {
    asm volatile("cp.async.bulk.shared::cluster.global.mbarrier::complete_tx::bytes [%0], [%1], %2, [%3];"
                 ::"r"(dst), "l"(src), "r"(bytes), "r"(bar) : "memory");
}
__device__ __forceinline__ void prefetch_l2(const void* src, uint32_t bytes) {
    asm volatile("cp.async.bulk.prefetch.L2.global [%0], %1;" ::"l"(src), "r"(bytes) : "memory");
}
__device__ __forceinline__ uint4 ldg128(const void* p) {
    uint4 v;
    asm volatile("ld.global.nc.v4.u32 {%0,%1,%2,%3}, [%4];" : "=r"(v.x), "=r"(v.y), "=r"(v.z), "=r"(v.w) : "l"(p));
    return v;
}
__device__ __forceinline__ uint32_t ldg16(const void* p) {
    uint32_t v;
    asm volatile("ld.global.nc.u16 %0, [%1];" : "=r"(v) : "l"(p));
    return v;
}
__device__ __forceinline__ uint32_t ldg32(const void* p) {
    uint32_t v;
    asm volatile("ld.global.nc.u32 %0, [%1];" : "=r"(v) : "l"(p));
    return v;
}
__device__ __forceinline__ uint4 ld_x4(const uint32_t* p) {
    uint4 v;
    asm volatile("ld.relaxed.gpu.global.v4.u32 {%0,%1,%2,%3}, [%4];" : "=r"(v.x), "=r"(v.y), "=r"(v.z), "=r"(v.w) : "l"(p) : "memory");
    return v;
}
__device__ __forceinline__ uint32_t tag_of(uint32_t epoch) {
    uint32_t t;
    asm volatile("mov.b32 %0, %1;" : "=r"(t) : "r"(epoch));
    return t;
}
__device__ __forceinline__ uint32_t tagged(float v, uint32_t tag) { return (__float_as_uint(v) & ~15u) | tag; }
__device__ __forceinline__ uint32_t tag_diff(const uint4& v, uint32_t tag) { return (v.x ^ tag) | (v.y ^ tag) | (v.z ^ tag) | (v.w ^ tag); }
__device__ __forceinline__ void st_x1(uint32_t* p, uint32_t a) {
    asm volatile("st.relaxed.gpu.global.u32 [%0], %1;" ::"l"(p), "r"(a) : "memory");
}
__device__ __forceinline__ void st_x2(uint32_t* p, uint32_t a, uint32_t b) {
    asm volatile("st.relaxed.gpu.global.v2.u32 [%0], {%1,%2};" ::"l"(p), "r"(a), "r"(b) : "memory");
}
__device__ __forceinline__ void st_x4(uint32_t* p, uint32_t a, uint32_t b, uint32_t c, uint32_t d) {
    asm volatile("st.relaxed.gpu.global.v4.u32 [%0], {%1,%2,%3,%4};" ::"l"(p), "r"(a), "r"(b), "r"(c), "r"(d) : "memory");
}
__device__ __forceinline__ uint32_t pack_bf16(float lo, float hi) {
    uint32_t r;
    asm("cvt.rn.bf16x2.f32 %0, %1, %2;" : "=r"(r) : "f"(hi), "f"(lo));
    return r;
}
__device__ __forceinline__ uint32_t pack_relu_bf16(float lo, float hi) {
    uint32_t r;
    asm("cvt.rn.relu.bf16x2.f32 %0, %1, %2;" : "=r"(r) : "f"(hi), "f"(lo));
    return r;
}
__device__ __forceinline__ uint32_t mul_bf16x2(uint32_t a, uint32_t b) {
    uint32_t r;
    asm("mul.rn.bf16x2 %0, %1, %2;" : "=r"(r) : "r"(a), "r"(b));
    return r;
}
__device__ __forceinline__ float link(float v, uint32_t dep, uint32_t zero) { return __uint_as_float(__float_as_uint(v) | (dep & zero)); }
__device__ __forceinline__ uint32_t gtime() {
    uint32_t t;
    asm volatile("mov.u32 %0, %%globaltimer_lo;" : "=r"(t));
    return t;
}
__device__ __forceinline__ float bf_lo(uint32_t v) { return __uint_as_float(v << 16); }
__device__ __forceinline__ float bf_hi(uint32_t v) { return __uint_as_float(v & 0xffff0000u); }
__device__ __forceinline__ float round_bf16(float v) { return __bfloat162float(__float2bfloat16_rn(v)); }
__device__ __forceinline__ float4 lds128(uint32_t a) {
    float4 v;
    asm volatile("ld.shared.v4.f32 {%0,%1,%2,%3}, [%4];" : "=f"(v.x), "=f"(v.y), "=f"(v.z), "=f"(v.w) : "r"(a));
    return v;
}
__device__ __forceinline__ float2 lds64(uint32_t a) {
    float2 v;
    asm volatile("ld.shared.v2.f32 {%0,%1}, [%2];" : "=f"(v.x), "=f"(v.y) : "r"(a));
    return v;
}
constexpr uint32_t LO_K128 = 1u << 16, LO_MN128 = 512u << 16, LO_CORE = 64u << 16;
constexpr uint32_t HI_SW128 = 64u | (1u << 30), HI_CORE = 8u;
__device__ __forceinline__ u64 mk_desc(uint32_t lo, uint32_t hi) { return ((u64)hi << 32) | lo; }
#define WG_FENCE() asm volatile("wgmma.fence.sync.aligned;" ::: "memory")
#define WG_COMMIT() asm volatile("wgmma.commit_group.sync.aligned;" ::: "memory")
#define WG_WAIT(n) asm volatile("wgmma.wait_group.sync.aligned %0;" ::"n"(n) : "memory")
#define R8(a, o) "+f"(a[o + 0]), "+f"(a[o + 1]), "+f"(a[o + 2]), "+f"(a[o + 3]), "+f"(a[o + 4]), "+f"(a[o + 5]), "+f"(a[o + 6]), "+f"(a[o + 7])
template <int TA, int TB>
__device__ __forceinline__ void mma128(float (&d)[64], u64 a, u64 b, uint32_t acc) {
    asm volatile(
        "{\n.reg .pred p;\nsetp.ne.u32 p, %66, 0;\n"
        "wgmma.mma_async.sync.aligned.m64n128k16.f32.bf16.bf16 "
        "{%0,%1,%2,%3,%4,%5,%6,%7,%8,%9,%10,%11,%12,%13,%14,%15,%16,%17,%18,%19,%20,%21,%22,%23,%24,%25,%26,%27,%28,%29,%30,%31,"
        "%32,%33,%34,%35,%36,%37,%38,%39,%40,%41,%42,%43,%44,%45,%46,%47,%48,%49,%50,%51,%52,%53,%54,%55,%56,%57,%58,%59,%60,%61,%62,%63},"
        " %64, %65, p, 1, 1, %67, %68;\n}"
        : R8(d, 0), R8(d, 8), R8(d, 16), R8(d, 24), R8(d, 32), R8(d, 40), R8(d, 48), R8(d, 56)
        : "l"(a), "l"(b), "r"(acc), "n"(TA), "n"(TB));
}
template <int TA, int TB>
__device__ __forceinline__ void mma112(float (&d)[64], u64 a, u64 b, uint32_t acc) {
    asm volatile(
        "{\n.reg .pred p;\nsetp.ne.u32 p, %58, 0;\n"
        "wgmma.mma_async.sync.aligned.m64n112k16.f32.bf16.bf16 "
        "{%0,%1,%2,%3,%4,%5,%6,%7,%8,%9,%10,%11,%12,%13,%14,%15,%16,%17,%18,%19,%20,%21,%22,%23,%24,%25,%26,%27,%28,%29,%30,%31,"
        "%32,%33,%34,%35,%36,%37,%38,%39,%40,%41,%42,%43,%44,%45,%46,%47,%48,%49,%50,%51,%52,%53,%54,%55},"
        " %56, %57, p, 1, 1, %59, %60;\n}"
        : R8(d, 0), R8(d, 8), R8(d, 16), R8(d, 24), R8(d, 32), R8(d, 40), R8(d, 48)
        : "l"(a), "l"(b), "r"(acc), "n"(TA), "n"(TB));
}
__device__ __forceinline__ void fence_regs(float (&d)[64]) {
#pragma unroll
    for (int i = 0; i < 64; i++) asm volatile("" : "+f"(d[i])::"memory");
}

__device__ __forceinline__ uint32_t w_slot(int i) { return 2u + 2u * (uint32_t)((i + 4) - 6 * (((i + 4) * 43) >> 8)); }
__device__ __forceinline__ uint32_t w_par(int i) { return (uint32_t)((i * 43) >> 8) & 1u; }
__device__ __forceinline__ uint32_t x_slot(int c) { return c == 0 ? 0u : (uint32_t)(2 * c - 1); }
__device__ __forceinline__ uint32_t p2_slot(int pos) { return (uint32_t)(pos - 14 * ((pos * 37) >> 9)); }
__device__ __forceinline__ uint32_t p2_par(int pos) { return ((0x2BFFu >> p2_slot(pos)) ^ (uint32_t)((pos * 37) >> 9)) & 1u; }
__device__ __forceinline__ int f_start(int j) { return j < 7 ? 176 * j : 1216; }

__device__ __forceinline__ void poll_bsum(const uint32_t* p, uint32_t tag, uint32_t (&v)[4]) {
    asm volatile(
        "{\n.reg .pred p;\n.reg .u32 c, t0, t1;\nmov.u32 c, 0;\n"
        "LP:\nld.relaxed.gpu.global.u32 %0, [%4];\nld.relaxed.gpu.global.u32 %1, [%4+4096];\n"
        "ld.relaxed.gpu.global.u32 %2, [%4+256];\nld.relaxed.gpu.global.u32 %3, [%4+4352];\n"
        "xor.b32 t0, %0, %5;\nxor.b32 t1, %1, %5;\nor.b32 t0, t0, t1;\nxor.b32 t1, %2, %5;\nor.b32 t0, t0, t1;\n"
        "xor.b32 t1, %3, %5;\nor.b32 t0, t0, t1;\nand.b32 t0, t0, 15;\n"
        "setp.eq.u32 p, t0, 0;\nvote.sync.all.pred p, p, 0xffffffff;\n@p bra LD;\n"
        "add.u32 c, c, 1;\nsetp.lt.u32 p, c, 0x20000;\n@p bra LP;\n" TRAP_S "\nLD:\n}"
        : "=&r"(v[0]), "=&r"(v[1]), "=&r"(v[2]), "=&r"(v[3]) : "l"(p), "r"(tag) : "memory");
}
__device__ __forceinline__ void cmul(float& re, float& im, float ar, float ai, float br, float bi) {
    re = ar * br - ai * bi;
    im = ar * bi + ai * br;
}

template <int N>
__device__ __forceinline__ void f_mma(float (&d)[64], u64 a, u64 b, uint32_t acc) {
    if (N == 128) mma128<0, 1>(d, a, b, acc);
    else mma112<0, 1>(d, a, b, acc);
}
__device__ __forceinline__ void lds64_if(bool c, float2& v, uint32_t a) {
    asm volatile("{\n.reg .pred p;\nsetp.ne.u32 p, %3, 0;\n@p ld.shared.v2.f32 {%0,%1}, [%2];\n}" : "+f"(v.x), "+f"(v.y) : "r"(a), "r"((uint32_t)c));
}
__device__ __forceinline__ void lds32_if(bool c, float& v, uint32_t a) {
    asm volatile("{\n.reg .pred p;\nsetp.ne.u32 p, %2, 0;\n@p ld.shared.f32 %0, [%1];\n}" : "+f"(v) : "r"(a), "r"((uint32_t)c));
}
template <int N>
__device__ __forceinline__ void f_mainloop(float (&a0)[64], float (&a1)[64], uint32_t sb, int fb, bool rel, float2 (&cg)[8], float2 (&cu)[8],
                                           float (&mn)[4], uint32_t ca, uint32_t sa) {
    constexpr uint32_t PAR = N == 128 ? 0xFCu : 0xC0u;
    const uint32_t A0 = (sb >> 4) + LO_K128, B0 = (sb >> 4) + LO_MN128;
    uint32_t la = A0, lb = B0 + (N == 128 ? 6 : 10) * 1024, pa = A0, pb = B0, ok = 0;
#pragma unroll 1
    for (int c = 0; c < 8; c++) {
        mbar_wait_if(ok, sb + B_FULL + ((lb - B0) >> 7), (PAR >> c) & 1u);
        const bool ld = c == 6;
        if (ld) mbar_wait(sb + B_CS, 0);
        const u64 da = mk_desc(la, HI_SW128), db = mk_desc(lb, HI_SW128);
        WG_FENCE();
        f_mma<N>(a0, da, db, c != 0);
        lds64_if(ld, cg[0], ca), lds64_if(ld, cu[0], ca + 704), lds64_if(ld, cg[1], ca + 32);
        f_mma<N>(a1, da + 512, db, c != 0);
        lds64_if(ld, cu[1], ca + 736), lds64_if(ld, cg[2], ca + 64), lds64_if(ld, cu[2], ca + 768);
        f_mma<N>(a0, da + 2, db + 128, 1);
        WG_COMMIT();
        WG_WAIT(1);
        if (c > 0 && rel) {
            mbar_arrive(sb + B_EMPTY + ((pb - B0) >> 7));
            if (N == 112) mbar_arrive(sb + B_EMPTY + ((pa - A0) >> 7));
        }
        WG_FENCE();
        f_mma<N>(a1, da + 514, db + 128, 1);
        lds64_if(ld, cg[3], ca + 96), lds64_if(ld, cu[3], ca + 800), lds64_if(ld, cg[4], ca + 128), lds64_if(ld, cu[4], ca + 832);
        f_mma<N>(a0, da + 4, db + 256, 1);
        lds64_if(ld, cg[5], ca + 160), lds64_if(ld, cu[5], ca + 864), lds64_if(ld, cg[6], ca + 192), lds64_if(ld, cu[6], ca + 896);
        f_mma<N>(a1, da + 516, db + 256, 1);
        pa = la;
        pb = lb;
        la += c ? 2048 : 1024;
        lb = lb == B0 + 12 * 1024 ? B0 + 2 * 1024 : lb + 2048;
        ok = mbar_test(sb + B_FULL + ((lb - B0) >> 7), (PAR >> (c + 1)) & 1u);
        if (c == 7 && fb < 2 && rel) mbar_arrive(sb + B_ORD + 8 * (2 * fb + 1));
        f_mma<N>(a0, da + 6, db + 384, 1);
        lds64_if(ld, cg[7], ca + 224), lds64_if(ld, cu[7], ca + 928);
        lds32_if(ld, mn[0], sa), lds32_if(ld, mn[1], sa + 16), lds32_if(ld, mn[2], sa + 128), lds32_if(ld, mn[3], sa + 144);
        f_mma<N>(a1, da + 518, db + 384, 1);
        WG_COMMIT();
    }
    WG_WAIT(0);
    if (rel) {
        mbar_arrive(sb + B_EMPTY + ((pb - B0) >> 7));
        if (N == 112) mbar_arrive(sb + B_EMPTY + ((pa - A0) >> 7));
    }
}

struct P2State {
    uint32_t s0, s1, s2;
    uint32_t r0, r2;
    bool ok, pend;
};
__device__ __forceinline__ void p2_begin(P2State& st, int pos) {
    st.ok = st.pend = false;
    st.r0 = st.r2 = 0;
    st.s0 = p2_slot(pos), st.s1 = p2_slot(pos + 1), st.s2 = p2_slot(pos + 2);
}
template <int TA, int TB, int NS>
__device__ __forceinline__ void p2_group(float (&acc)[64], uint32_t sb, int pos, bool notfirst, bool rel, P2State& st) {
    if (!st.ok) {
        WG_WAIT(0);
        mbar_arrive2_if(st.pend && rel, st.r0, st.r2);
        st.pend = false;
#pragma unroll 1
        for (int u = 0; u < 3; u++) mbar_wait(sb + B_FULL + 8 * p2_slot(pos + u), p2_par(pos + u));
    }
    constexpr uint32_t LB = (1024 >> 4) + (TB ? LO_MN128 : LO_K128);
    constexpr int ST = TB ? 128 : 2;
    const u64 da = mk_desc((1024 >> 4) + LO_CORE + st.s0 * 1024, HI_CORE);
    const u64 db = mk_desc(LB + st.s1 * 1024, HI_SW128), dc = mk_desc(LB + st.s2 * 1024, HI_SW128);
    WG_FENCE();
#pragma unroll
    for (int kk = 0; kk < NS; kk++) mma128<TA, TB>(acc, da + kk * 128, db + kk * ST, kk ? 1u : (uint32_t)notfirst);
    WG_COMMIT();
    WG_WAIT(1);
    mbar_arrive2_if(st.pend && rel, st.r0, st.r2);
    WG_FENCE();
    mma128<TA, TB>(acc, da + 512, dc, 1);
    const uint32_t r1 = sb + B_EMPTY + 8 * st.s1;
    st.r0 = sb + B_EMPTY + 8 * st.s0;
    st.r2 = sb + B_EMPTY + 8 * st.s2;
    st.pend = true;
    st.s0 = p2_slot(pos + 3);
    st.s1 = p2_slot(pos + 4);
    st.s2 = p2_slot(pos + 5);
    uint32_t t = mbar_test(sb + B_FULL + 8 * st.s0, p2_par(pos + 3));
    t &= mbar_test(sb + B_FULL + 8 * st.s1, p2_par(pos + 4));
    t &= mbar_test(sb + B_FULL + 8 * st.s2, p2_par(pos + 5));
    st.ok = __all_sync(0xffffffffu, t);
#pragma unroll
    for (int kk = 1; kk < NS - 1; kk++) mma128<TA, TB>(acc, da + 512 + kk * 128, dc + kk * ST, 1);
    WG_COMMIT();
    WG_WAIT(1);
    if (rel) mbar_arrive(r1);
    WG_FENCE();
    mma128<TA, TB>(acc, da + 512 + (NS - 1) * 128, dc + (NS - 1) * ST, 1);
    WG_COMMIT();
}

__global__ void __launch_bounds__(384, 1) s5_reglu_kernel(const __grid_constant__ Params P) {
    extern __shared__ __align__(1024) unsigned char smem[];
    constexpr uint32_t sb = 1024;
    const int tid = threadIdx.x, lane = tid & 31;
    if (tid == 0) {
        asm volatile("prefetch.tensormap [%0];" ::"l"(&P.tmX) : "memory");
        asm volatile("prefetch.tensormap [%0];" ::"l"(&P.tmB) : "memory");
    }
    const int warp = __shfl_sync(0xffffffffu, tid >> 5, 0);
    const int bid = blockIdx.x;
    const int half = bid >> 6;
    const int m = 2 * ((bid >> 3) & 7) + (bid & 1);
    const int nt = (bid >> 1) & 3;
    const int j = 4 * half + nt;
    const int g8 = lane >> 2, q = lane & 3;

    if (warp == 9 && elect_one()) {
        mbar_init(sb + B_FULL, 1u);
        mbar_init(sb + B_FULL + 8, 1u);
        mbar_init(sb + B_FULL + 8 * w_slot(0), 1u);
        mbar_expect_tx(sb + B_FULL, SLOT);
        tma5(sb, &P.tmX, sb + B_FULL, 0, m);
        PROF_ONE(53);
        mbar_expect_tx(sb + B_FULL + 8 * w_slot(0), SLOT);
        tma4(sb + w_slot(0) * SLOT, &P.tmB, sb + B_FULL + 8 * w_slot(0), 0, 8 * j);
        tma4(sb + w_slot(0) * SLOT + 8192, &P.tmB, sb + B_FULL + 8 * w_slot(0), 64, 8 * j);
        mbar_expect_tx(sb + B_FULL + 8, SLOT);
        tma5(sb + SLOT, &P.tmX, sb + B_FULL + 8, 64, m);
    }
    __syncwarp();
    const int p0 = 64 * j + 8 * (warp & 3) + g8;
    uint32_t lam[6];
    if (warp < 4) {
        lam[0] = ldg16(P.lam_re + p0), lam[1] = ldg16(P.lam_re + p0 + 32), lam[2] = ldg16(P.lam_im + p0);
        lam[3] = ldg16(P.lam_im + p0 + 32), lam[4] = ldg16(P.log_dt + p0), lam[5] = ldg16(P.log_dt + p0 + 32);
    }
    if (warp >= 8) {
    asm volatile("setmaxnreg.dec.sync.aligned.u32 88;");
    if (warp == 9) {
        if (elect_one()) {
#pragma unroll
            for (int b = 2; b < NSLOT; b++)
                if (b != (int)w_slot(0)) mbar_init(sb + B_FULL + 8 * b, 1u);
            asm volatile("fence.mbarrier_init.release.cluster;" ::: "memory");
        }
        __syncwarp();
        asm volatile("bar.arrive 1, 192;\nbar.arrive 4, 192;\nbar.arrive 5, 128;" ::: "memory");
        if (elect_one()) {
#pragma unroll 1
            for (int c = 2; c < 8; c++) {
                mbar_expect_tx(sb + B_FULL + 8 * (2 * c - 1), SLOT);
                tma5(sb + (2 * c - 1) * SLOT, &P.tmX, sb + B_FULL + 8 * (2 * c - 1), 64 * c, m);
                if (!(c & 1)) {
                    const uint32_t ws = c == 2 ? 12 : c - 2;
                    mbar_expect_tx(sb + B_FULL + 8 * ws, SLOT);
                    tma4(sb + ws * SLOT, &P.tmB, sb + B_FULL + 8 * ws, 64 * c, 8 * j);
                    tma4(sb + ws * SLOT + 8192, &P.tmB, sb + B_FULL + 8 * ws, 64 * c + 64, 8 * j);
                }
            }
        }
        __syncwarp();
        asm volatile("bar.sync 2, 64;" ::: "memory");
        if (lane < 2) st_x4(P.flag + (8 * m + j) * 8 + 4 * lane, 0u, 0u, 0u, 0u);
        if (lane == 0) {
            prefetch_l2(P.Wg + bid * 5504, 11008);
            prefetch_l2(P.Wu + bid * 5504, 11008);
        }
        __syncwarp();
        PROFW(54);
    }
    if (warp == 8) {
        if (elect_one()) {
#pragma unroll
            for (int b = NSLOT; b < NBAR; b++) mbar_init(sb + OFF_BAR + 8 * b, b < NBAR - 3 ? 4u : (b == NBAR - 3 ? 96u : (b == NBAR - 2 ? 32u : 128u)));
            asm volatile("fence.mbarrier_init.release.cluster;" ::: "memory");
        }
        __syncwarp();
        asm volatile("bar.arrive 1, 192;\nbar.arrive 4, 192;\nbar.arrive 5, 128;" ::: "memory");
    }
    const uint32_t epoch = ld_epoch(P.sync);
    if (warp >= 9) {
        uint4 v[16];
        const int job = min(bid + 128 * (warp - 9), 351);
        const int rb = job & 7, cgrp = job >> 3, jup = cgrp >= 22, col = 64 * (cgrp - 22 * jup) + 8 * g8;
        uint32_t* cdst = P.csum + (2 * rb + jup) * 1408 + col + 4 * q;
        const bool cpub = q < 2 && bid + 128 * (warp - 9) < 352;
        if (cpub) st_x4(cdst, 0u, 0u, 0u, 0u);
        if (warp > 9) {
            const int ridx = 8 * bid + 4 * (warp - 10) + (lane >> 3);
            const bf16* src = (bid < 64 ? P.B1 : P.B2) + (size_t)(ridx & 511) * 512 + 8 * (lane & 7);
#pragma unroll
            for (int t = 0; t < 8; t++) v[t] = ldg128(src + 64 * t);
            float b0 = 0.f, b1 = 0.f;
#pragma unroll
            for (int t = 0; t < 8; t++) {
                b0 += (bf_lo(v[t].x) + bf_lo(v[t].y)) + (bf_lo(v[t].z) + bf_lo(v[t].w));
                b1 += (bf_hi(v[t].x) + bf_hi(v[t].y)) + (bf_hi(v[t].z) + bf_hi(v[t].w));
            }
            b0 += b1;
#pragma unroll
            for (int k = 1; k < 8; k <<= 1) b0 += __shfl_xor_sync(0xffffffffu, b0, k);
            if (!(lane & 7)) st_x2(P.bsum + 2 * ridx, tagged(b0, tag_of(epoch)), 0u);
            if (warp == 10) PROFW(57);
            asm volatile("bar.sync 5, 128;" ::: "memory");
        }
        const uint32_t tag = tag_of(epoch);
        const char* base = (const char*)((jup ? P.Wu : P.Wg) + (size_t)(64 * rb + q) * FF + min(col, FF - 8));
        mbar_wait(sb + B_FULL + 8 * 9, 0);
        if (warp == 10) PROFW(61);
#pragma unroll
        for (int t = 0; t < 16; t++) v[t] = ldg128(base + t * (8 * FF));
        if (warp == 9) {
            mbar_wait(sb + B_FULL + 8 * 13, 0);
            uint4 a, b;
            uint32_t spins = 0;
            do {
                a = ld_x4(P.stats + 256 * m + 4 * lane);
                b = ld_x4(P.stats + 256 * m + 128 + 4 * lane);
                spin_check(spins);
            } while (__any_sync(0xffffffffu, (tag_diff(a, tag) | tag_diff(b, tag)) & 15u));
            const uint32_t d = sb + OFF_STATS + q * 272 + g8 * 16;
            asm volatile("st.shared.v4.b32 [%0], {%1,%2,%3,%4};" ::"r"(d), "r"(a.x), "r"(a.y), "r"(a.z), "r"(a.w) : "memory");
            asm volatile("st.shared.v4.b32 [%0], {%1,%2,%3,%4};" ::"r"(d + 128), "r"(b.x), "r"(b.y), "r"(b.z), "r"(b.w) : "memory");
            mbar_arrive(sb + B_STATS);
            PROFW(42);
        }
        {
            uint32_t dep = 0;
#pragma unroll
            for (int t = 0; t < 16; t++) dep |= v[t].x;
            float cs[8];
#pragma unroll
            for (int e = 0; e < 4; e++) {
                dep &= P.zero;
                const uint32_t sh = 16u + dep, msk = 0xffff0000u | dep;
                float lo = 0.f, hi = 0.f;
#pragma unroll
                for (int t = 0; t < 16; t++) {
                    const uint32_t ww = e == 0 ? v[t].x : (e == 1 ? v[t].y : (e == 2 ? v[t].z : v[t].w));
                    lo += __uint_as_float(ww << sh);
                    hi += __uint_as_float(ww & msk);
                }
                cs[2 * e] = lo, cs[2 * e + 1] = hi;
                dep = __float_as_uint(hi);
            }
#pragma unroll
            for (int k = 0; k < 4; k++) {
                const float snd = (q & 1) ? cs[k] : cs[k + 4], kp = (q & 1) ? cs[k + 4] : cs[k];
                cs[k] = kp + __shfl_xor_sync(0xffffffffu, snd, 1);
                cs[k] += __shfl_xor_sync(0xffffffffu, cs[k], 2);
            }
            if (cpub) st_x4(cdst, tagged(cs[0], tag), tagged(cs[1], tag), tagged(cs[2], tag), tagged(cs[3], tag));
            if (warp == 10) PROFW(44);
        }
        {
            const int it = min(30 * (warp - 9) + min(lane, 29), 87), up = it >= 44;
            const uint32_t* src = P.csum + up * 1408 + f_start(j) + 4 * (it - 44 * up);
            uint4 v[8];
            uint32_t spins = 0, bad;
            do {
                bad = 0;
#pragma unroll
                for (int k = 0; k < 8; k++) v[k] = ld_x4(src + k * 2816);
#pragma unroll
                for (int k = 0; k < 8; k++) bad |= tag_diff(v[k], tag);
                spin_check(spins);
            } while (__any_sync(0xffffffffu, bad & 15u));
            float4 r = make_float4(0.f, 0.f, 0.f, 0.f);
#pragma unroll
            for (int k = 0; k < 8; k++)
                r.x += __uint_as_float(v[k].x), r.y += __uint_as_float(v[k].y), r.z += __uint_as_float(v[k].z), r.w += __uint_as_float(v[k].w);
            asm volatile("st.shared.v4.f32 [%0], {%1,%2,%3,%4};" ::"r"(sb + OFF_CS + it * 16), "f"(r.x), "f"(r.y), "f"(r.z), "f"(r.w) : "memory");
            mbar_arrive(sb + B_CS);
            if (warp == 9) PROFW(43);
        }
    }

    {
        if (warp == 8) {
            const int f0 = f_start(j);
            asm volatile("bar.sync 2, 64;" ::: "memory");
#pragma unroll 1
            for (int i = 4; i < 32; i++) {
                const uint32_t ws = w_slot(i);
                const uint32_t fullb = sb + B_FULL + 8 * ws, dst = sb + ws * SLOT;
                if (i >= 6) mbar_wait(sb + B_EMPTY + 8 * ws, w_par(i) ^ 1u);
                if (elect_one()) {
                    mbar_expect_tx(fullb, SLOT);
                    if (i >= 12 && i < 16) {
                        tma4(dst, &P.tmB, fullb, 128 * (i & 3), 8 * j + 4);
                        tma4(dst + 8192, &P.tmB, fullb, 128 * (i & 3) + 64, 8 * j + 4);
                    } else {
                        const int fb = i < 12 ? 0 : (i < 24 ? 1 : 2);
                        const int c = (i < 12 ? i - 4 : i) & 7;
                        tma2(dst, &P.tmWg, fullb, f0 + 64 * fb, 64 * c);
                        tma2(dst + 8192, &P.tmWu, fullb, f0 + 64 * fb, 64 * c);
                    }
                }
                __syncwarp();
                if (i == 5) PROFW(59);
            }
            PROFW(40);
        } else if (warp == 9) {
            if (lane == 0) {
                asm volatile("prefetch.tensormap [%0];" ::"l"(&P.tmWd) : "memory");
                asm volatile("prefetch.tensormap [%0];" ::"l"(&P.tmC1) : "memory");
                asm volatile("prefetch.tensormap [%0];" ::"l"(&P.tmC2) : "memory");
                asm volatile("prefetch.tensormap [%0];" ::"l"(&P.tmXh) : "memory");
                prefetch_l2(P.C1 + bid * 2048, 4096);
                prefetch_l2(P.C2 + bid * 2048, 4096);
                prefetch_l2(P.Wd + bid * 5504, 11008);
            }
#pragma unroll 1
            for (int k = 0; k < 4; k++) {
                mbar_wait(sb + B_PUB + 8 * k, 0);
                if (lane == 0)
                    asm volatile("st.release.gpu.global.u32 [%0], %1;" ::"l"(P.flag + (8 * m + j) * 8 + k), "r"(epoch) : "memory");
                __syncwarp();
                PROFW(45 + k);
            }
            return;
        } else {
            if ((uint32_t)__cvta_generic_to_shared(smem) != sb) asm volatile("trap;");
        }
        const int u = warp == 10 ? 0 : (warp == 8 ? 2 : 1);
        const unsigned char* hsrc = P.h + (size_t)(2 * m + half) * (KG_TOT * 1024);
        const CUtensorMap* tmC = u == 1 ? &P.tmC1 : &P.tmC2;
        uint32_t ready = 0;
        mbar_wait(sb + B_XDONE, 0);
#pragma unroll 1
        for (int g = 0; g < 20; g++) {
            const bool is_s = g < 4 || g >= 16;
            const int ks = g < 4 ? g : g - 12, kd = g - 4, blk = kd >> 2, ja = 2 * (kd & 3);
            const int pos = 3 * g + u + (g >= 4);
            if (g == 4 && u == 0) {
                mbar_wait(sb + B_EMPTY + 8 * 12, p2_par(12) ^ 1u);
                if (elect_one()) {
                    mbar_expect_tx(sb + B_FULL + 8 * 12, SLOT);
                    tma5h(sb + 12 * SLOT, &P.tmXh, sb + B_FULL + 8 * 12, 128 * nt, 8 * half, m);
                    tma5h(sb + 12 * SLOT + 8192, &P.tmXh, sb + B_FULL + 8 * 12, 128 * nt + 64, 8 * half, m);
                }
                __syncwarp();
            }
            const uint32_t s = p2_slot(pos);
            const uint32_t fullb = sb + B_FULL + 8 * s, dst = sb + s * SLOT;
            const int fa = f_start(ja) + 64 * blk, fb2 = f_start(ja + 1) + 64 * blk;
            if (u == 0) {
                const uint32_t need = is_s ? (0x100u << ks) : (3u << ((blk ? 8 + 8 * blk : 0) + ja));
                if ((ready & need) != need) {
                    uint32_t spins = 0;
                    do {
                        uint32_t v;
                        asm volatile("ld.acquire.gpu.global.u32 %0, [%1];" : "=r"(v) : "l"(P.flag + (8 * m + (lane & 7)) * 8 + (lane >> 3)) : "memory");
                        ready = __ballot_sync(0xffffffffu, v == epoch);
                        spin_check(spins);
                    } while ((ready & need) != need);
                    __syncwarp();
                    asm volatile("fence.proxy.async.global;" ::: "memory");
                }
            }
            mbar_wait(fullb, p2_par(pos) ^ 1u);
            mbar_wait(sb + B_EMPTY + 8 * s, p2_par(pos) ^ 1u);
            if (elect_one()) {
                if (u == 0) {
                    const uint32_t bytes = (is_s || blk < 2) ? 8192u : (ja < 6 ? 6144u : 4096u);
                    mbar_expect_tx(fullb, 2 * bytes);
                    bulk_g2s(dst, hsrc + (is_s ? ks * 16384 : 131072 + fa * 128), bytes, fullb);
                    bulk_g2s(dst + 8192, hsrc + (is_s ? ks * 16384 + 8192 : 131072 + fb2 * 128), bytes, fullb);
                } else {
                    mbar_expect_tx(fullb, SLOT);
                    if (is_s) tma2(dst, tmC, fullb, 64 * ks, 128 * nt);
                    else tma3(dst, &P.tmWd, fullb, 0, u == 1 ? fa : fb2, 2 * nt);
                }
            }
            __syncwarp();
        }
        if (warp == 8 && lane == 0) {
            const unsigned t = atomicAdd(P.sync + 32, 1u);
            if ((t & 127u) == 127u) *(volatile unsigned*)P.sync = epoch == 15u ? 1u : epoch + 1u;
        }
        if (warp == 8) PROFW(41);
    }
    } else {
        asm volatile("setmaxnreg.inc.sync.aligned.u32 208;");
        const uint32_t epoch = ld_epoch(P.sync);
        const int wg = warp >> 2, w = warp & 3;
        const bool rel = lane == 0;
        unsigned char* hdst = P.h + (size_t)(2 * m) * (KG_TOT * 1024) + lane * 4;
        float a0[64], a1[64];
        uint32_t tag;

        if (wg == 1) {
            const int n = 16 * j + 4 * w + (lane >> 3);
            if (!(lane & 7)) st_x2(P.stats + 2 * (128 * m + n), 0u, 0u);
            asm volatile("bar.sync 4, 192;" ::: "memory");
            const uint32_t xoff = sb + n * 128 + (lane & 7) * 16;
            float s0 = 0.f, s1 = 0.f, q0 = 0.f, q1 = 0.f;
            mbar_wait(sb + B_FULL, 0);
            tag = tag_of(epoch);
#pragma unroll 1
            for (int c = 0; c < 8; c++) {
                mbar_wait(sb + B_FULL + 8 * x_slot(c), 0);
                const float4 t = lds128(xoff + x_slot(c) * SLOT);
#pragma unroll
                for (int e = 0; e < 4; e++) {
                    const uint32_t ww = __float_as_uint(e == 0 ? t.x : (e == 1 ? t.y : (e == 2 ? t.z : t.w)));
                    const float lo = bf_lo(ww), hi = bf_hi(ww);
                    s0 += lo, s1 += hi;
                    q0 = fmaf(lo, lo, q0), q1 = fmaf(hi, hi, q1);
                }
            }
            PROF(56);
            s0 += s1, q0 += q1;
#pragma unroll
            for (int k = 1; k < 8; k <<= 1) {
                s0 += __shfl_xor_sync(0xffffffffu, s0, k);
                q0 += __shfl_xor_sync(0xffffffffu, q0, k);
            }
            {
                const float mean = s0 * (1.f / 512.f);
                const float var = fmaxf(q0 * (1.f / 512.f) - mean * mean, 0.f);
                float sd, r;
                asm("sqrt.approx.f32 %0, %1;" : "=f"(sd) : "f"(round_bf16(round_bf16(var) + 1e-5f)));
                asm("rcp.approx.f32 %0, %1;" : "=f"(r) : "f"(round_bf16(sd)));
                if (!(lane & 7)) st_x2(P.stats + 2 * (128 * m + n), tagged(round_bf16(mean), tag), tagged(r, tag));
            }
            PROF(16);
        } else {
            if (q == 3) {
                st_x2(P.E + 2 * (m * 512 + p0), 0u, 0u);
                st_x2(P.E + 2 * (m * 512 + p0 + 32), 0u, 0u);
            }
            float kc[14], kn[14];
            asm volatile("bar.sync 1, 192;" ::: "memory");
            uint32_t bs[4] = {0u, 0u, 0u, 0u};
            float4 stv[16];
#pragma unroll 1
            for (int hb = 0; hb < 2; hb++) {
                const int p = p0 + 32 * hb;
                if (hb == 1) mbar_wait(sb + B_ORD + 8, 0);
                PROF(0 + 4 * hb);
                {
                    constexpr uint32_t A0 = (sb >> 4) + LO_K128;
                    mbar_wait(sb + B_FULL + 8 * 10, 0);
                    mbar_wait(sb + B_FULL, 0);
                    WG_FENCE();
#pragma unroll
                    for (int kk = 0; kk < 4; kk++) mma128<0, 0>(a0, mk_desc(A0 + 10 * 1024 + 2 * kk, HI_SW128), mk_desc(A0 + 2 * kk, HI_SW128), kk != 0);
                    WG_COMMIT();
                    uint32_t w0 = 10, w1 = 12, pw = 0;
                    bool ok = false;
#pragma unroll 1
                    for (int it = 0; it < 3; it++) {
                        if (!ok) {
                            mbar_wait(sb + B_FULL + 8 * (4 * it + 1), 0);
                            mbar_wait(sb + B_FULL + 8 * (4 * it + 3), 0);
                            mbar_wait(sb + B_FULL + 8 * w1, 0);
                        }
                        const u64 da = mk_desc(A0 + w0 * 1024 + 512, HI_SW128), db = mk_desc(A0 + (4 * it + 1) * 1024, HI_SW128);
                        const u64 dc = mk_desc(A0 + w1 * 1024, HI_SW128);
                        WG_FENCE();
#pragma unroll
                        for (int kk = 0; kk < 4; kk++) mma128<0, 0>(a0, da + 2 * kk, db + 2 * kk, 1);
                        const uint32_t rb = sb + B_EMPTY + 8 * pw;
                        pw = w0;
                        w0 = w1;
                        w1 = it == 0 ? 2 : 4;
                        const uint32_t t = mbar_test(sb + B_FULL + 8 * (4 * it + 5), 0) & mbar_test(sb + B_FULL + 8 * min(4 * it + 7, 13), 0) &
                                           mbar_test(sb + B_FULL + 8 * w1, 0);
                        mma128<0, 0>(a0, dc, db + 2048, 1);
                        mma128<0, 0>(a0, dc + 2, db + 2050, 1);
                        ok = __all_sync(0xffffffffu, t);
                        mma128<0, 0>(a0, dc + 4, db + 2052, 1);
                        mma128<0, 0>(a0, dc + 6, db + 2054, 1);
                        WG_COMMIT();
                        WG_WAIT(1);
                        if (it > 0 && rel) mbar_arrive(rb);
                    }
                    if (!ok) mbar_wait(sb + B_FULL + 8 * 13, 0);
                    if (rel) mbar_arrive(sb + B_ORD + 16 * hb);
                    WG_FENCE();
#pragma unroll
                    for (int kk = 0; kk < 4; kk++)
                        mma128<0, 0>(a0, mk_desc(A0 + 4 * 1024 + 512 + 2 * kk, HI_SW128), mk_desc(A0 + 13 * 1024 + 2 * kk, HI_SW128), 1);
                    WG_COMMIT();
                    WG_WAIT(1);
                    if (rel) mbar_arrive(sb + B_EMPTY + 8 * 2);
                    WG_WAIT(0);
                    if (rel) mbar_arrive(sb + B_EMPTY + 8 * 4);
                }
                fence_regs(a0);
                PROF(1 + 4 * hb);
                if (hb == 0) {
                    tag = tag_of(epoch);
                    poll_bsum(P.bsum + 2 * p0, tag, bs);
                    PROF(50);
#pragma unroll 1
            for (int h = 1; h >= 0; h--) {
#pragma unroll
                for (int k = 0; k < 14; k++) kn[k] = kc[k];
                const float Lr = bf_lo(h ? lam[1] : lam[0]), Li = bf_lo(h ? lam[3] : lam[2]);
                const float dt = round_bf16(expf(bf_lo(h ? lam[5] : lam[4])));
                float sn, cs;
                sincospif(dt * Li * 0.318309886183790672f, &sn, &cs);
                const float e = expf(dt * Lr);
                const float lr = e * cs, li = e * sn;
                const float inv = __fdividef(1.f, Lr * Lr + Li * Li);
                kc[0] = lr;
                kc[1] = li * P.sw;
                kc[2] = 2.f * P.sw * ((lr - 1.f) * Lr + li * Li) * inv;
                kc[3] = -2.f * (li * Lr - (lr - 1.f) * Li) * inv;
                float ar = kc[0], ai = kc[1];
#pragma unroll
                for (int k = 0; k < 5; k++) cmul(ar, ai, ar, ai, ar, ai);
                kc[4] = ar, kc[5] = ai;
                cmul(kc[6], kc[7], ar, ai, ar, ai);
                cmul(kc[8], kc[9], kc[6], kc[7], kc[6], kc[7]);
                cmul(kc[10], kc[11], (q & 1) ? ar : 1.f, (q & 1) ? ai : 0.f, (q & 2) ? kc[6] : 1.f, (q & 2) ? kc[7] : 0.f);
                float br, bi;
                cmul(ar, ai, kc[8], kc[9], kc[8], kc[9]);
                cmul(ar, ai, ar, ai, ar, ai);
                cmul(br, bi, ar, ai, ar, ai);
                cmul(kc[12], kc[13], (q & 1) ? ar : 1.f, (q & 1) ? ai : 0.f, (q & 2) ? br : 1.f, (q & 2) ? bi : 0.f);
            }
                    PROF(51);
                    mbar_wait(sb + B_STATS, 0);
                    PROF(52);
#pragma unroll
                    for (int jn = 0; jn < 16; jn++) stv[jn] = lds128(sb + OFF_STATS + q * 272 + jn * 16);
                }
                const float lr = kc[0], li = kc[1], k1 = kc[2], k2 = kc[3], l32r = kc[4], l32i = kc[5], l64r = kc[6], l64i = kc[7];
                const float gr = kc[8], gi = kc[9], lqr = kc[10], lqi = kc[11], gqr = kc[12], gqi = kc[13];
                const float csa = __uint_as_float(hb ? bs[2] : bs[0]), csb = __uint_as_float(hb ? bs[3] : bs[1]);
                float ha = 0.f, hbv = 0.f;
#pragma unroll
                for (int jn = 0; jn < 16; jn++) {
                    const float4 st = stv[jn];
                    const float cla = link(csa, __float_as_uint(ha), P.zero), clb = link(csb, __float_as_uint(ha), P.zero);
#pragma unroll
                    for (int e = 0; e < 2; e++) {
                        const float mean = e ? st.z : st.x, r = e ? st.w : st.y;
                        const float va = r * fmaf(-mean, cla, a0[4 * jn + e]);
                        const float vb = r * fmaf(-mean, clb, a0[4 * jn + 2 + e]);
                        a0[4 * jn + e] = va;
                        a0[4 * jn + 2 + e] = vb;
                        const float na = fmaf(lr, ha, fmaf(-li, hbv, va));
                        hbv = fmaf(lr, hbv, fmaf(li, ha, vb));
                        ha = na;
                    }
                }
                {
                    float ta = __shfl_up_sync(0xffffffffu, ha, 1, 4), tb = __shfl_up_sync(0xffffffffu, hbv, 1, 4);
                    if (q >= 1) {
                        ha = fmaf(l32r, ta, fmaf(-l32i, tb, ha));
                        hbv = fmaf(l32r, tb, fmaf(l32i, ta, hbv));
                    }
                    ta = __shfl_up_sync(0xffffffffu, ha, 2, 4), tb = __shfl_up_sync(0xffffffffu, hbv, 2, 4);
                    if (q >= 2) {
                        ha = fmaf(l64r, ta, fmaf(-l64i, tb, ha));
                        hbv = fmaf(l64r, tb, fmaf(l64i, ta, hbv));
                    }
                }
                if (q == 3) st_x2(P.E + 2 * (m * 512 + p), tagged(ha, tag), tagged(hbv, tag));
                float pa = __shfl_up_sync(0xffffffffu, ha, 1, 4), pb = __shfl_up_sync(0xffffffffu, hbv, 1, 4);
                if (q == 0) pa = 0.f, pb = 0.f;
                PROF(2 + 4 * hb);
                {
                    float k1l = link(k1, __float_as_uint(pa), P.zero), k2l = link(k2, __float_as_uint(pa), P.zero);
#pragma unroll
                    for (int jn = 0; jn < 16; jn++) {
#pragma unroll
                        for (int e = 0; e < 2; e++) {
                            const float va = a0[4 * jn + e], vb = a0[4 * jn + 2 + e];
                            a0[4 * jn + e] = fmaf(k1l, va, k2l * vb);
                            a0[4 * jn + 2 + e] = fmaf(k2l, va, -k1l * vb);
                        }
                        if (jn & 1) {
                            const uint32_t d = __float_as_uint(a0[4 * jn]) | __float_as_uint(a0[4 * jn + 3]) | __float_as_uint(a0[4 * jn - 2]);
                            k1l = link(k1, d, P.zero);
                            k2l = link(k2, d, P.zero);
                        }
                    }
                }
                PROF(hb ? 58 : 55);
                {
                    uint32_t ea[4], eb[4];
                    asm volatile(
                        "{\n.reg .pred p, v0, v1, v2, v3;\n.reg .u32 c, t0, t1;\nmov.u32 c, 0;\n"
                        "setp.gt.s32 v0, %9, 0;\nsetp.gt.s32 v1, %9, 1;\nsetp.gt.s32 v2, %9, 2;\nsetp.gt.s32 v3, %9, 3;\n"
                        "mov.u32 %0, %10;\nmov.u32 %1, %10;\nmov.u32 %2, %10;\nmov.u32 %3, %10;\n"
                        "mov.u32 %4, %10;\nmov.u32 %5, %10;\nmov.u32 %6, %10;\nmov.u32 %7, %10;\n"
                        "LP:\n@v0 ld.relaxed.gpu.global.v2.u32 {%0, %4}, [%8];\n@v1 ld.relaxed.gpu.global.v2.u32 {%1, %5}, [%8+-4096];\n"
                        "@v2 ld.relaxed.gpu.global.v2.u32 {%2, %6}, [%8+-8192];\n@v3 ld.relaxed.gpu.global.v2.u32 {%3, %7}, [%8+-12288];\n"
                        "xor.b32 t0, %0, %10;\nxor.b32 t1, %1, %10;\nor.b32 t0, t0, t1;\nxor.b32 t1, %2, %10;\nor.b32 t0, t0, t1;\n"
                        "xor.b32 t1, %3, %10;\nor.b32 t0, t0, t1;\nxor.b32 t1, %4, %10;\nor.b32 t0, t0, t1;\nxor.b32 t1, %5, %10;\nor.b32 t0, t0, t1;\n"
                        "xor.b32 t1, %6, %10;\nor.b32 t0, t0, t1;\nxor.b32 t1, %7, %10;\nor.b32 t0, t0, t1;\nand.b32 t0, t0, 15;\n"
                        "setp.eq.u32 p, t0, 0;\nvote.sync.all.pred p, p, 0xffffffff;\n"
                        "@p bra LD;\nadd.u32 c, c, 1;\nsetp.lt.u32 p, c, 0x20000;\n@p bra LP;\n" TRAP_S "\nLD:\n}"
                        : "=&r"(ea[0]), "=&r"(ea[1]), "=&r"(ea[2]), "=&r"(ea[3]), "=&r"(eb[0]), "=&r"(eb[1]), "=&r"(eb[2]), "=&r"(eb[3])
                        : "l"(P.E + 2 * ((m - 1 - 4 * q) * 512 + p)), "r"(m - 4 * q), "r"(tag) : "memory");
                    float ca = __uint_as_float(ea[3]), cb = __uint_as_float(eb[3]);
#pragma unroll
                    for (int k = 2; k >= 0; k--) {
                        const float na = fmaf(gr, ca, fmaf(-gi, cb, __uint_as_float(ea[k])));
                        cb = fmaf(gr, cb, fmaf(gi, ca, __uint_as_float(eb[k])));
                        ca = na;
                    }
                    float Ha, Hb;
                    cmul(Ha, Hb, gqr, gqi, ca, cb);
                    Ha += __shfl_xor_sync(0xffffffffu, Ha, 1);
                    Hb += __shfl_xor_sync(0xffffffffu, Hb, 1);
                    Ha += __shfl_xor_sync(0xffffffffu, Ha, 2);
                    Hb += __shfl_xor_sync(0xffffffffu, Hb, 2);
                    pa = fmaf(lqr, Ha, fmaf(-lqi, Hb, pa));
                    pb = fmaf(lqr, Hb, fmaf(lqi, Ha, pb));
                }
                PROF(hb ? 39 : 63);
                ha = fmaf(k1, pa, k2 * pb);
                hbv = fmaf(k2, pa, -k1 * pb);
                unsigned char* dst = hdst + (16 * j + 4 * hb + w) * 1024;
#pragma unroll
                for (int jn = 0; jn < 16; jn++) {
                    const float x0 = fmaf(lr, ha, fmaf(li, hbv, a0[4 * jn]));
                    const float y0 = fmaf(lr, hbv, fmaf(-li, ha, a0[4 * jn + 2]));
                    ha = fmaf(lr, x0, fmaf(li, y0, a0[4 * jn + 1]));
                    hbv = fmaf(lr, y0, fmaf(-li, x0, a0[4 * jn + 3]));
                    unsigned char* d = dst + (jn >> 3) * (KG_TOT * 1024) + (jn & 7) * 128;
                    *(uint32_t*)d = pack_bf16(x0, ha);
                    *(uint32_t*)(d + 8192) = pack_bf16(y0, hbv);
                }
#pragma unroll
                for (int k = 0; k < 14; k++) kc[k] = kn[k];
                PROF(3 + 4 * hb);
            }
            __syncwarp();
            if (rel) mbar_arrive(sb + B_PUB + 8);
        }

#pragma unroll
        for (int k = 0; k < 64; k++) a1[k] = 0.f;
        fence_regs(a1);
#pragma unroll 1
        for (int fb = wg ? 0 : 2; fb < (wg ? 2 : 3); fb++) {
            const uint32_t sa = sb + OFF_STATS + (g8 >> 1) * 272 + (4 * w + (g8 & 1)) * 8;
            const uint32_t ca = sb + OFF_CS + (64 * fb + 2 * q) * 4;
            float2 cgv[8], cuv[8];
            float mn[4] = {0.f, 0.f, 0.f, 0.f};
#pragma unroll
            for (int k = 0; k < 8; k++) cgv[k] = cuv[k] = make_float2(0.f, 0.f);
            mbar_wait(sb + B_ORD + 8 * (fb == 2 ? 3 : 2 * fb), 0);
            if (fb == 2 && tid == 0) st_x1(P.flag + (8 * m + j) * 8 + 4, (gtime() & ~15u) | tag);
            PROF(17 + 4 * fb);
            if (fb < 2) f_mainloop<128>(a0, a1, sb, fb, rel, cgv, cuv, mn, ca, sa);
            else f_mainloop<112>(a0, a1, sb, fb, rel, cgv, cuv, mn, ca, sa);
            fence_regs(a0);
            fence_regs(a1);
            PROF(18 + 4 * fb);
            if (fb == 1 && rel) mbar_arrive(sb + B_XDONE);
            const int nj = fb < 2 ? 8 : (j < 6 ? 6 : 4);
            unsigned char* dst = hdst + (128 + ((f_start(j) + 64 * fb) >> 3)) * 1024 + 2 * w * 128;
            uint32_t hp = 0;
#pragma unroll
            for (int jf = 0; jf < 8; jf++) {
                if (jf < nj) {
                    const float2 cg = cgv[jf], cu = cuv[jf];
                    unsigned char* d = dst + jf * 1024;
#define FFN_PAIR(A, o, mm)                                                                                        \
    mul_bf16x2(pack_relu_bf16(fmaf(-(mm), cg.x, A[4 * jf + (o)]), fmaf(-(mm), cg.y, A[4 * jf + (o) + 1])),         \
               pack_bf16(fmaf(-(mm), cu.x, A[32 + 4 * jf + (o)]), fmaf(-(mm), cu.y, A[32 + 4 * jf + (o) + 1])))
                    float ma = link(mn[0], hp, P.zero), mb = link(mn[1], hp, P.zero);
                    *(uint32_t*)d = FFN_PAIR(a0, 0, ma);
                    *(uint32_t*)(d + 128) = hp = FFN_PAIR(a0, 2, mb);
                    ma = link(mn[2], hp, P.zero), mb = link(mn[3], hp, P.zero);
                    *(uint32_t*)(d + KG_TOT * 1024) = FFN_PAIR(a1, 0, ma);
                    *(uint32_t*)(d + KG_TOT * 1024 + 128) = hp = FFN_PAIR(a1, 2, mb);
#undef FFN_PAIR
                }
            }
            __syncwarp();
            if (rel) mbar_arrive(sb + B_PUB + (fb ? 8 + 8 * fb : 0));
            PROF(19 + 4 * fb);
        }

        const int tok0 = 32 * (g8 >> 1) + 16 * half + 4 * w + (g8 & 1);
        const uint32_t sa = sb + OFF_STATS + (g8 >> 1) * 16 + tok0 * 8;
        const float2 st0 = lds64(sa), st1 = lds64(sa + 16);
        if (wg == 0) {
            P2State st;
            p2_begin(st, 13);
            mbar_wait(sb + B_ORD + 8, 1);
#pragma unroll 1
            for (int k = 0; k < 8; k++) {
                p2_group<0, 1, 4>(a0, sb, 13 + 3 * k, k != 0, rel, st);
                if (k == 0) PROF(29);
                if (k == 4) PROF(32);
            }
            PROF(36);
#pragma unroll 1
            for (int k = 0; k < 3; k++) {
                p2_group<0, 1, 3>(a0, sb, 37 + 3 * k, true, rel, st);
                if (k == 0) PROF(33);
            }
            if (rel) mbar_arrive(sb + B_ORD);
            p2_group<0, 1, 2>(a0, sb, 46, true, rel, st);
            WG_WAIT(0);
            fence_regs(a0);
            mbar_arrive2_if(rel, st.r0, st.r2);
            PROF(30);
            uint32_t gp[32];
            const float z0 = 0.5f * st0.y * st0.y, z1 = 0.5f * st1.y * st1.y;
            uint32_t gl = 0;
#pragma unroll
            for (int k = 0; k < 32; k++) {
                const float zs = link((k & 1) ? z1 : z0, gl, P.zero);
                const float u0 = a0[2 * k] * zs, u1 = a0[2 * k + 1] * zs;
                float t0, t1;
                asm("tanh.approx.f32 %0, %1;" : "=f"(t0) : "f"(u0));
                asm("tanh.approx.f32 %0, %1;" : "=f"(t1) : "f"(u1));
                gp[k] = pack_bf16(fmaf(u0, t0, u0), fmaf(u1, t1, u1));
                if (k & 1) gl = gp[k];
            }
            asm volatile("bar.sync 3, 128;" ::: "memory");
#pragma unroll
            for (int k = 0; k < 8; k++)
                asm volatile("st.shared.v4.b32 [%0], {%1,%2,%3,%4};" ::"r"(sb + OFF_G + k * 2048 + tid * 16), "r"(gp[4 * k]),
                             "r"(gp[4 * k + 1]), "r"(gp[4 * k + 2]), "r"(gp[4 * k + 3]) : "memory");
            mbar_arrive(sb + B_G);
            PROF(31);
        } else {
            if (w == 0) {
                asm volatile(
                    "{\n.reg .pred p;\n.reg .u32 c, t0, t1, u0, u1, u2, u3;\nmov.u32 c, 0;\n"
                    "LP:\nld.relaxed.gpu.global.u32 u0, [%0];\nld.relaxed.gpu.global.u32 u1, [%0+1024];\n"
                    "ld.relaxed.gpu.global.u32 u2, [%0+2048];\nld.relaxed.gpu.global.u32 u3, [%0+3072];\n"
                    "xor.b32 t0, u0, %1;\nxor.b32 t1, u1, %1;\nor.b32 t0, t0, t1;\nxor.b32 t1, u2, %1;\nor.b32 t0, t0, t1;\n"
                    "xor.b32 t1, u3, %1;\nor.b32 t0, t0, t1;\nand.b32 t0, t0, 15;\nsetp.eq.u32 p, t0, 0;\n"
                    "vote.sync.all.pred p, p, 0xffffffff;\n@p bra LD;\n"
                    "add.u32 c, c, 1;\nsetp.lt.u32 p, c, 0x20000;\n@p bra LP;\n" TRAP_S "\nLD:\n"
                    "sub.u32 u0, u0, %2;\nsub.u32 u1, u1, %2;\nsub.u32 u2, u2, %2;\nsub.u32 u3, u3, %2;\n"
                    "max.s32 u0, u0, u1;\nmax.s32 u2, u2, u3;\nmax.s32 u0, u0, u2;\nredux.sync.max.s32 u0, u0, 0xffffffff;\n"
                    "add.u32 u0, u0, %2;\nadd.u32 u0, u0, %3;\nmov.u32 c, 0;\n"
                    "LT:\nmov.u32 t0, %%globaltimer_lo;\nsub.u32 t0, t0, u0;\nsetp.ge.s32 p, t0, 0;\n"
                    "vote.sync.all.pred p, p, 0xffffffff;\n@p bra LE;\n"
                    "add.u32 c, c, 1;\nsetp.lt.u32 p, c, 0x20000;\n@p bra LT;\nLE:\n}"
                    ::"l"(P.flag + 8 * lane + 4), "r"(tag), "r"(gtime()), "n"(GO_DELAY_NS) : "memory");
            }
            asm volatile("bar.sync 6, 128;" ::: "memory");
            PROF(35);
#pragma unroll 1
            for (int run = 0; run < 2; run++) {
                P2State st;
                p2_begin(st, 49 * run);
                if (run) mbar_wait(sb + B_ORD, 1);
#pragma unroll 1
                for (int k = 0; k < 4; k++) {
                    if (k == 3 && rel) mbar_arrive(sb + B_ORD + 8);
                    p2_group<1, 0, 4>(a0, sb, 49 * run + 3 * k, (run | k) != 0, rel, st);
                    if (k == 0) PROF(run ? 14 : 9);
                }
                if (run == 0) {
                    PROF(11);
                    WG_WAIT(0);
                    mbar_arrive2_if(rel, st.r0, st.r2);
                    fence_regs(a0);
                    uint32_t xv[32];
                    mbar_wait(sb + B_FULL + 8 * 12, p2_par(12));
                    const uint32_t row = sb + 12 * SLOT + (16 * w + (lane & 15)) * 128;
#pragma unroll
                    for (int k = 0; k < 8; k++)
                        asm volatile("ldmatrix.sync.aligned.m8n8.x4.shared.b16 {%0,%1,%2,%3}, [%4];"
                                     : "=r"(xv[4 * k]), "=r"(xv[4 * k + 1]), "=r"(xv[4 * k + 2]), "=r"(xv[4 * k + 3])
                                     : "r"(row + (k >> 2) * 8192 + ((((2 * k + (lane >> 4)) & 7) ^ (lane & 7)) << 4)) : "memory");
                    if (lane == (int)((xv[3] | xv[7] | xv[11] | xv[15] | xv[19] | xv[23] | xv[27] | xv[31]) & P.zero)) mbar_arrive(sb + B_EMPTY + 8 * 12);
                    uint32_t dv[16];
#pragma unroll
                    for (int jd = 0; jd < 16; jd++) dv[jd] = ldg32(P.dskip + 128 * nt + 2 * q + 8 * jd);
                    const float mr0 = -st0.x * st0.y, mr1 = -st1.x * st1.y;
                    uint32_t al = 0;
#pragma unroll
                    for (int k = 0; k < 32; k++) {
                        const uint32_t xl = xv[k] | (al & P.zero);
                        a1[2 * k] = bf_lo(xl);
                        a1[2 * k + 1] = bf_hi(xl);
                        a0[2 * k] = fmaf(fmaf(a1[2 * k], (k & 1) ? st1.y : st0.y, (k & 1) ? mr1 : mr0), bf_lo(dv[k >> 1]), a0[2 * k]);
                        a0[2 * k + 1] = fmaf(fmaf(a1[2 * k + 1], (k & 1) ? st1.y : st0.y, (k & 1) ? mr1 : mr0), bf_hi(dv[k >> 1]), a0[2 * k + 1]);
                        al = __float_as_uint(a0[2 * k + 1]);
                    }
                    fence_regs(a0);
                    fence_regs(a1);
                    PROF(38);
                }
            }
            PROF(10);
            mbar_wait(sb + B_G, 0);
            float4 gq[8];
#pragma unroll
            for (int k = 0; k < 8; k++) gq[k] = lds128(sb + OFF_G + k * 2048 + (tid & 127) * 16);
            WG_WAIT(0);
            fence_regs(a0);
            PROF(12);
            float* o = P.out + (size_t)(128 * m + tok0) * 512 + 128 * nt + 2 * q;
#pragma unroll
            for (int k = 0; k < 8; k++) {
#pragma unroll
                for (int e = 0; e < 4; e++) {
                    const uint32_t gp = __float_as_uint(e == 0 ? gq[k].x : (e == 1 ? gq[k].y : (e == 2 ? gq[k].z : gq[k].w)));
                    float2 v;
                    v.x = fmaf(a0[8 * k + 2 * e], bf_lo(gp), a1[8 * k + 2 * e]);
                    v.y = fmaf(a0[8 * k + 2 * e + 1], bf_hi(gp), a1[8 * k + 2 * e + 1]);
                    *(float2*)(o + (e & 1) * 1024 + 8 * (2 * k + (e >> 1))) = v;
                }
            }
            PROF(13);
        }
    }
}

typedef CUresult (*EncodeFn)(CUtensorMap*, CUtensorMapDataType, cuuint32_t, void*, const cuuint64_t*, const cuuint64_t*,
                             const cuuint32_t*, const cuuint32_t*, CUtensorMapInterleave, CUtensorMapSwizzle,
                             CUtensorMapL2promotion, CUtensorMapFloatOOBfill);

void encode(EncodeFn fn, CUtensorMap* tm, const void* base, int rank, const cuuint64_t* dims, const cuuint64_t* strides,
            const cuuint32_t* box) {
    const cuuint32_t es[5] = {1, 1, 1, 1, 1};
    fn(tm, CU_TENSOR_MAP_DATA_TYPE_BFLOAT16, (cuuint32_t)rank, const_cast<void*>(base), dims, strides, box, es,
       CU_TENSOR_MAP_INTERLEAVE_NONE, CU_TENSOR_MAP_SWIZZLE_128B, CU_TENSOR_MAP_L2_PROMOTION_L2_256B,
       CU_TENSOR_MAP_FLOAT_OOB_FILL_NONE);
}

}

extern "C" void kernel_launch(void* const* d_in, const int* in_sizes, int n_in, void* d_out, int out_size) {
    (void)in_sizes; (void)n_in; (void)out_size;
    static EncodeFn fn = nullptr;
    static void* sym[8];
    if (!fn) {
        cudaGetSymbolAddress(&sym[0], g_h);
        cudaGetSymbolAddress(&sym[1], g_bsum);
        cudaGetSymbolAddress(&sym[2], g_csum);
        cudaGetSymbolAddress(&sym[3], g_E);
        cudaGetSymbolAddress(&sym[4], g_flag);
        cudaGetSymbolAddress(&sym[5], g_sync);
        cudaGetSymbolAddress(&sym[6], g_stats);
        void* f = nullptr;
        cudaDriverEntryPointQueryResult qr;
        cudaGetDriverEntryPoint("cuTensorMapEncodeTiled", &f, cudaEnableDefault, &qr);
        fn = (EncodeFn)f;
        cudaFuncSetAttribute(s5_reglu_kernel, cudaFuncAttributeMaxDynamicSharedMemorySize, (int)SMEM_BYTES);
    }
    Params P;
    const bf16* Bre = (const bf16*)d_in[3];
    const bf16* Bim = (const bf16*)d_in[4];
    const bool re_first = Bre < Bim;
    P.x = (const bf16*)d_in[0];
    P.lam_re = (const bf16*)d_in[1];
    P.lam_im = (const bf16*)d_in[2];
    P.B1 = re_first ? Bre : Bim;
    P.B2 = re_first ? Bim : Bre;
    P.C1 = (const bf16*)d_in[re_first ? 5 : 6];
    P.C2 = (const bf16*)d_in[re_first ? 6 : 5];
    P.log_dt = (const bf16*)d_in[7];
    P.dskip = (const bf16*)d_in[8];
    P.Wg = (const bf16*)d_in[10];
    P.Wu = (const bf16*)d_in[11];
    P.Wd = (const bf16*)d_in[12];
    P.out = (float*)d_out;
    P.h = (unsigned char*)sym[0];
    P.bsum = (uint32_t*)sym[1];
    P.csum = (uint32_t*)sym[2];
    P.E = (uint32_t*)sym[3];
    P.flag = (unsigned*)sym[4];
    P.sync = (unsigned*)sym[5];
    P.stats = (uint32_t*)sym[6];
    P.zero = 0;
    P.sw = re_first ? 1.f : -1.f;
    {
        const cuuint64_t d[5] = {512, 2, 4, 16, 16}, s[4] = {1024, 32 * 1024, 2 * 1024, 128 * 1024};
        const cuuint32_t b[5] = {64, 2, 4, 16, 1};
        encode(fn, &P.tmX, P.x, 5, d, s, b);
        const cuuint32_t bh[5] = {64, 2, 4, 8, 1};
        encode(fn, &P.tmXh, P.x, 5, d, s, bh);
    }
    {
        const cuuint64_t d[4] = {512, 8, 2, 64}, s[3] = {1024, (cuuint64_t)((const char*)P.B2 - (const char*)P.B1), 8192};
        const cuuint32_t b[4] = {64, 8, 2, 4};
        encode(fn, &P.tmB, P.B1, 4, d, s, b);
    }
    {
        const cuuint64_t d[2] = {FF, 512}, s[1] = {FF * 2};
        const cuuint32_t b[2] = {64, 64};
        encode(fn, &P.tmWg, P.Wg, 2, d, s, b);
        encode(fn, &P.tmWu, P.Wu, 2, d, s, b);
    }
    {
        const cuuint64_t d[2] = {512, 512}, s[1] = {1024};
        const cuuint32_t b[2] = {64, 128};
        encode(fn, &P.tmC1, P.C1, 2, d, s, b);
        encode(fn, &P.tmC2, P.C2, 2, d, s, b);
    }
    {
        const cuuint64_t d[3] = {64, FF, 8}, s[2] = {1024, 128};
        const cuuint32_t b[3] = {64, 64, 2};
        encode(fn, &P.tmWd, P.Wd, 3, d, s, b);
    }
    s5_reglu_kernel<<<128, 384, SMEM_BYTES, cudaStreamPerThread>>>(P);
}
```
